```python
import torch

def _softmax(x, axis=-1):
    return torch.softmax(x, dim=axis)
def _gelu(x):
    return torch.nn.functional.gelu(x, approximate="tanh")
def _silu(x):
    return torch.nn.functional.silu(x)
def _sigmoid(x):
    return torch.sigmoid(x)
def _layernorm(x, axis=-1, eps=1e-5):
    m = x.mean(dim=axis, keepdim=True)
    v = x.var(dim=axis, keepdim=True, unbiased=False)
    return (x - m) / torch.sqrt(v + eps)
def _scatter_add(tgt, idx, src, axis=0):
    return tgt.clone().index_add_(axis, idx, src)
def _segment_sum(src, seg, n):
    out = torch.zeros((n,) + src.shape[1:], dtype=src.dtype)
    return out.index_add_(0, seg, src)
def _pad(x, pw):
    flat = tuple(v for pair in reversed(pw) for v in pair)
    return torch.nn.functional.pad(x, flat)

kernel_name = 'standalone__self_sup_conv_stem_wavlm__speech'

def setup_inputs():

    _w = (lambda a: (lambda t: t.to(torch.bfloat16) if t.is_floating_point() else t)(torch.as_tensor(a)))
    B, T, D, K = 2, 1000, 512, 15
    scale = (K * D) ** -0.5
    return {
        "x": _w((lambda *s: torch.randn(*s, dtype=torch.bfloat16) * 0.05)(B, T, D)),
        "w": _w((lambda *s: torch.randn(*s, dtype=torch.bfloat16) * 0.05)(K, D, D) * scale),
        "gn_gamma": _w((lambda *s: torch.randn(*s, dtype=torch.bfloat16) * 0.05)(D) * 0.1 + 1.0),
        "gn_beta": _w((lambda *s: torch.randn(*s, dtype=torch.bfloat16) * 0.05)(D) * 0.1),
    }

def reference(x, w, gn_gamma, gn_beta):
    B, T, D = x.shape
    K = w.shape[0]
    s = 2
    L = (T - K) // s + 1
    h = torch.einsum('blc,cd->bld', x[:, 0:s * L:s, :], w[0])
    for i in range(1, K):
        h = h + torch.einsum('blc,cd->bld', x[:, i:i + s * L:s, :], w[i])
    mu = torch.einsum('bld->bd', h)[:, None, :] / L
    var = torch.einsum('bld->bd', (h - mu) ** 2)[:, None, :] / L
    h = (h - mu) / torch.sqrt(var + 1e-5)
    h = h * gn_gamma[None, None, :] + gn_beta[None, None, :]
    return _gelu(h)
```

```cpp
#include <cuda_runtime.h>
#include <cuda_bf16.h>
#include <cuda.h>
#include <stdint.h>

namespace {

constexpr int kB = 2, kT = 1000, kD = 512, kTaps = 15, kL = 493;
constexpr int kXRows = 136;
constexpr int kXPhBytes = kXRows * 128;
constexpr int kXBlkBytes = 2 * kXPhBytes;
constexpr int kXSlots = 2;
constexpr int kWBytes = 64 * 128;
constexpr int kStages = kTaps;
constexpr int kBlocks = 4;
constexpr int kSplitT = 8;
constexpr int kSplitN = kTaps - kSplitT;
constexpr int kHead = 5;
constexpr int kXOddT = 6;
constexpr int kTail = kL - 7 * 64;

constexpr int kOffX = 0;
constexpr int kOffW = kOffX + kXSlots * kXBlkBytes;
__host__ __device__ constexpr int x_slot(int cb) { return kOffX + ((cb & 1) ^ 1) * kXBlkBytes; }
constexpr int kOffRecv = kOffW + kStages * kWBytes;
constexpr int kRecvBytes = 8192;
constexpr int kOffStage = kOffRecv + kRecvBytes;
constexpr int kOffBar = kOffStage + 8192;
constexpr int kSmemBytes = kOffBar + 640 + 1024;

constexpr int kBarFullW = 0;
constexpr int kBarEmptyW = kBarFullW + 8 * kStages;
constexpr int kBarRecv = kBarEmptyW + 8 * kStages;
constexpr int kBarAux = kBarRecv + 8;
constexpr int kOffAux = 320;

constexpr int kThreads = 256;
constexpr int kSpinLimit = 1 << 22;

#define PACE0 700
#define PACE1 190
#define PACE_W1 720
#define POLL_REL 320

__device__ uint4 g_stats[16 * 8 * 32];

__device__ __forceinline__ uint32_t smem_u32(const void* p) { return (uint32_t)__cvta_generic_to_shared(p); }
__device__ __forceinline__ uint32_t clock32() {
  uint32_t c;
  asm volatile("mov.u32 %0, %%clock;" : "=r"(c)::"memory");
  return c;
}
__device__ __forceinline__ void spin_until(uint32_t t) { while ((int)(clock32() - t) < 0) {} }
__device__ __forceinline__ void mbar_init(uint32_t bar, uint32_t cnt) {
  asm volatile("mbarrier.init.shared::cta.b64 [%0], %1;" ::"r"(bar), "r"(cnt) : "memory");
}
__device__ __forceinline__ void mbar_expect_tx(uint32_t bar, uint32_t bytes) {
  asm volatile("mbarrier.arrive.expect_tx.shared::cta.b64 _, [%0], %1;" ::"r"(bar), "r"(bytes) : "memory");
}
__device__ __forceinline__ void mbar_arrive(uint32_t bar) {
  asm volatile("mbarrier.arrive.shared::cta.b64 _, [%0];" ::"r"(bar) : "memory");
}
__device__ __forceinline__ void mbar_arrive_if(uint32_t bar, bool pred) {
  asm volatile("{\n.reg .pred p;\nsetp.ne.u32 p, %1, 0;\n@p mbarrier.arrive.shared::cta.b64 _, [%0];\n}"
               ::"r"(bar), "r"((uint32_t)pred) : "memory");
}
__device__ __forceinline__ void mbar_wait(uint32_t bar, uint32_t parity) {
  asm volatile("{\n.reg .pred p;\n.reg .u32 n;\n"
               "mbarrier.try_wait.parity.shared::cta.b64 p, [%0], %1;\n"
               "@p bra WDONE;\n"
               "mov.u32 n, 0;\n"
               "WLOOP:\n"
               "mbarrier.try_wait.parity.shared::cta.b64 p, [%0], %1;\n"
               "@p bra WDONE;\n"
               "add.u32 n, n, 1;\n"
               "setp.lt.u32 p, n, 4194304;\n"
               "@p bra WLOOP;\n"
               "trap;\n"
               "WDONE:\n}" ::"r"(bar), "r"(parity) : "memory");
}
__device__ __forceinline__ bool elect_one() {
  uint32_t p;
  asm volatile("{\n.reg .pred P;\nelect.sync _|P, 0xffffffff;\nselp.u32 %0, 1, 0, P;\n}" : "=r"(p));
  return p;
}
__device__ __forceinline__ void tma2d(uint32_t dst, const CUtensorMap* tm, int c0, int c1, uint32_t bar) {
  asm volatile("cp.async.bulk.tensor.2d.shared::cluster.global.mbarrier::complete_tx::bytes [%0], [%1, {%3, %4}], [%2];"
               ::"r"(dst), "l"(tm), "r"(bar), "r"(c0), "r"(c1) : "memory");
}
__device__ __forceinline__ void tma4d(uint32_t dst, const CUtensorMap* tm, int c0, int c1, int c2, int c3, uint32_t bar) {
  asm volatile("cp.async.bulk.tensor.4d.shared::cluster.global.mbarrier::complete_tx::bytes [%0], [%1, {%3, %4, %5, %6}], [%2];"
               ::"r"(dst), "l"(tm), "r"(bar), "r"(c0), "r"(c1), "r"(c2), "r"(c3) : "memory");
}
__device__ __forceinline__ void wg_fence() { asm volatile("wgmma.fence.sync.aligned;" ::: "memory"); }
__device__ __forceinline__ void wg_commit() { asm volatile("wgmma.commit_group.sync.aligned;" ::: "memory"); }
template <int N> __device__ __forceinline__ void wg_wait() { asm volatile("wgmma.wait_group.sync.aligned %0;" ::"n"(N) : "memory"); }

__device__ __forceinline__ uint32_t make_desc(uint32_t addr) { return ((addr & 0x3FFFF) >> 4) | (1u << 16); }
constexpr uint32_t kAStage = kWBytes >> 4, kAK16 = 2048 >> 4;
constexpr uint32_t kBRow = 128 >> 4, kBK16 = 32 >> 4;

__device__ __forceinline__ void wgmma_m64n128k16(float (&d)[64], uint32_t descA, uint32_t descB, int scaleD) {
  asm volatile(
    "{\n"
    ".reg .pred p;\n"
    ".reg .b64 da, db;\n"
    "mov.b64 da, {%64, 0x40000040};\n"
    "mov.b64 db, {%65, 0x40000040};\n"
    "setp.ne.b32 p, %66, 0;\n"
    "wgmma.mma_async.sync.aligned.m64n128k16.f32.bf16.bf16 "
    "{%0, %1, %2, %3, %4, %5, %6, %7, "
    "%8, %9, %10, %11, %12, %13, %14, %15, "
    "%16, %17, %18, %19, %20, %21, %22, %23, "
    "%24, %25, %26, %27, %28, %29, %30, %31, "
    "%32, %33, %34, %35, %36, %37, %38, %39, "
    "%40, %41, %42, %43, %44, %45, %46, %47, "
    "%48, %49, %50, %51, %52, %53, %54, %55, "
    "%56, %57, %58, %59, %60, %61, %62, %63"
    "}, da, db, p, 1, 1, 1, 0;\n"
    "}\n"
    : "+f"(d[0]), "+f"(d[1]), "+f"(d[2]), "+f"(d[3]), "+f"(d[4]), "+f"(d[5]), "+f"(d[6]), "+f"(d[7]),
      "+f"(d[8]), "+f"(d[9]), "+f"(d[10]), "+f"(d[11]), "+f"(d[12]), "+f"(d[13]), "+f"(d[14]), "+f"(d[15]),
      "+f"(d[16]), "+f"(d[17]), "+f"(d[18]), "+f"(d[19]), "+f"(d[20]), "+f"(d[21]), "+f"(d[22]), "+f"(d[23]),
      "+f"(d[24]), "+f"(d[25]), "+f"(d[26]), "+f"(d[27]), "+f"(d[28]), "+f"(d[29]), "+f"(d[30]), "+f"(d[31]),
      "+f"(d[32]), "+f"(d[33]), "+f"(d[34]), "+f"(d[35]), "+f"(d[36]), "+f"(d[37]), "+f"(d[38]), "+f"(d[39]),
      "+f"(d[40]), "+f"(d[41]), "+f"(d[42]), "+f"(d[43]), "+f"(d[44]), "+f"(d[45]), "+f"(d[46]), "+f"(d[47]),
      "+f"(d[48]), "+f"(d[49]), "+f"(d[50]), "+f"(d[51]), "+f"(d[52]), "+f"(d[53]), "+f"(d[54]), "+f"(d[55]),
      "+f"(d[56]), "+f"(d[57]), "+f"(d[58]), "+f"(d[59]), "+f"(d[60]), "+f"(d[61]), "+f"(d[62]), "+f"(d[63])
    : "r"(descA), "r"(descB), "r"(scaleD));
}

__device__ __forceinline__ void wgmma_m64n64k16(float (&d)[32], uint32_t descA, uint32_t descB, int scaleD) {
  asm volatile(
    "{\n"
    ".reg .pred p;\n"
    ".reg .b64 da, db;\n"
    "mov.b64 da, {%32, 0x40000040};\n"
    "mov.b64 db, {%33, 0x40000040};\n"
    "setp.ne.b32 p, %34, 0;\n"
    "wgmma.mma_async.sync.aligned.m64n64k16.f32.bf16.bf16 "
    "{%0, %1, %2, %3, %4, %5, %6, %7, "
    "%8, %9, %10, %11, %12, %13, %14, %15, "
    "%16, %17, %18, %19, %20, %21, %22, %23, "
    "%24, %25, %26, %27, %28, %29, %30, %31"
    "}, da, db, p, 1, 1, 1, 0;\n"
    "}\n"
    : "+f"(d[0]), "+f"(d[1]), "+f"(d[2]), "+f"(d[3]), "+f"(d[4]), "+f"(d[5]), "+f"(d[6]), "+f"(d[7]),
      "+f"(d[8]), "+f"(d[9]), "+f"(d[10]), "+f"(d[11]), "+f"(d[12]), "+f"(d[13]), "+f"(d[14]), "+f"(d[15]),
      "+f"(d[16]), "+f"(d[17]), "+f"(d[18]), "+f"(d[19]), "+f"(d[20]), "+f"(d[21]), "+f"(d[22]), "+f"(d[23]),
      "+f"(d[24]), "+f"(d[25]), "+f"(d[26]), "+f"(d[27]), "+f"(d[28]), "+f"(d[29]), "+f"(d[30]), "+f"(d[31])
    : "r"(descA), "r"(descB), "r"(scaleD));
}

__device__ __forceinline__ void st_rec(uint4* p, uint4 v) {
  asm volatile("st.relaxed.gpu.global.v4.u32 [%0], {%1, %2, %3, %4};" ::"l"(p), "r"(v.x), "r"(v.y), "r"(v.z), "r"(v.w) : "memory");
}
__device__ __forceinline__ uint4 ld_rec(const uint4* p) {
  uint4 v;
  asm volatile("ld.relaxed.gpu.global.v4.u32 {%0, %1, %2, %3}, [%4];" : "=r"(v.x), "=r"(v.y), "=r"(v.z), "=r"(v.w) : "l"(p) : "memory");
  return v;
}
__device__ __forceinline__ uint4 lds128(uint32_t addr) {
  uint4 v;
  asm volatile("ld.shared.v4.u32 {%0, %1, %2, %3}, [%4];" : "=r"(v.x), "=r"(v.y), "=r"(v.z), "=r"(v.w) : "r"(addr) : "memory");
  return v;
}
__device__ __forceinline__ uint32_t pack_bf16(float lo, float hi) {
  __nv_bfloat162 h = __floats2bfloat162_rn(lo, hi);
  return *reinterpret_cast<uint32_t*>(&h);
}
__device__ __forceinline__ float bf16_lo(uint32_t x) { return __uint_as_float(x << 16); }
__device__ __forceinline__ float bf16_hi(uint32_t x) { return __uint_as_float(x & 0xffff0000u); }

__device__ __forceinline__ float gelu_tanh_half(float h) {
  constexpr float k0 = 0.7978845608028654f, k1 = k0 * 0.044715f;
  float t;
  asm("tanh.approx.f32 %0, %1;" : "=f"(t) : "f"(h * fmaf(h * h, 8.f * k1, 2.f * k0)));
  return fmaf(h, t, h);
}

__global__ void __cluster_dims__(2, 1, 1) __launch_bounds__(kThreads, 1)
conv_stem_kernel(const __grid_constant__ CUtensorMap tmx, const __grid_constant__ CUtensorMap tmw,
                 const __nv_bfloat16* __restrict__ gamma, const __nv_bfloat16* __restrict__ beta,
                 __nv_bfloat16* __restrict__ out) {
  extern __shared__ uint8_t smem_raw[];
  const uint32_t base = (smem_u32(smem_raw) + 1023u) & ~1023u;
  const uint32_t bars = base + kOffBar;
  const int warp = __shfl_sync(0xffffffffu, threadIdx.x >> 5, 0);
  const int lane = threadIdx.x & 31;
  const int kh = blockIdx.x & 1;
  const int cl = blockIdx.x >> 1;
  const int dt = cl & 7, lt = (cl >> 3) & 3, b = cl >> 5;
  const uint32_t c_entry = clock32();

  const int c0 = kh * 256, l0 = lt * 128, d0 = dt * 64;
  uint32_t dO = make_desc(base + x_slot(kBlocks - 1) + kXPhBytes + kh * (64 * 128));
  uint32_t dP = make_desc(base + x_slot(kBlocks) + kh * (64 * 128));

  if (warp == 0) {
    if (elect_one()) {
      mbar_init(bars + kBarFullW, 1);
      asm volatile("fence.mbarrier_init.release.cluster;" ::: "memory");
      mbar_expect_tx(bars + kBarFullW, kWBytes + kXPhBytes);
      tma2d(base + kOffW, &tmw, d0, c0, bars + kBarFullW);
      tma4d(base + x_slot(0), &tmx, c0, 0, l0, b, bars + kBarFullW);
#pragma unroll
      for (int i = 0; i < kStages; i++) {
        if (i > 0) mbar_init(bars + kBarFullW + 8 * i, 1);
        mbar_init(bars + kBarEmptyW + 8 * i, 4);
      }
      mbar_init(bars + kBarRecv, 1);
      mbar_init(bars + kBarAux, 1);
      asm volatile("fence.mbarrier_init.release.cluster;" ::: "memory");
      mbar_expect_tx(bars + kBarRecv, kRecvBytes);
    }
    __syncwarp();
    asm volatile("bar.arrive 1, 192;" ::: "memory");
  }
  asm volatile("barrier.cluster.arrive.relaxed.aligned;" ::: "memory");

  if (warp == 0) {
    if (elect_one()) {
#pragma unroll 1
      for (int t = 1; t < kTaps; t++) {
        const uint32_t fb = bars + kBarFullW + 8 * t;
        spin_until(c_entry + (t == 1 ? PACE_W1 : PACE0 + PACE1 * t));
        mbar_expect_tx(fb, kWBytes + (t == kXOddT ? kXPhBytes : 0));
        tma2d(base + kOffW + t * kWBytes, &tmw, d0, (t < 8 ? 2 * t : 2 * t - 15) * kD + c0, fb);
        if (t == kXOddT) tma4d(base + x_slot(0) + kXPhBytes, &tmx, c0, 1, l0, b, fb);
      }
    }
    if (elect_one()) {
#pragma unroll 1
      for (int cb = 1; cb < kBlocks; cb++) {
        const uint32_t xdst = base + x_slot(cb);
        const int krow = c0 + cb * 64;
        uint32_t fb = bars + kBarFullW, wdst = base + kOffW;
#pragma unroll 1
        for (int t = 0; t < kTaps; t++, fb += 8, wdst += kWBytes) {
          const bool wrap = (t + 2 >= kTaps);
          mbar_wait(fb + (kBarEmptyW - kBarFullW) + 16 - (wrap ? 8 * kTaps : 0), (wrap ? cb : cb - 1) & 1);
          const bool with_x = (t == 0 || t == kXOddT);
          mbar_expect_tx(fb, kWBytes + (with_x ? kXPhBytes : 0));
          tma2d(wdst, &tmw, d0, (t < 8 ? 2 * t : 2 * t - 15) * kD + krow, fb);
          if (with_x) tma4d(xdst + (t ? kXPhBytes : 0), &tmx, krow, t ? 1 : 0, l0, b, fb);
        }
      }
      const int prow = (c0 ^ 256) + (kBlocks - 1) * 64;
#pragma unroll 1
      for (int t = 0; t < kSplitN; t++) {
        mbar_wait(bars + kBarEmptyW + 8 * max(t, 2), (kBlocks - 1) & 1);
        if (t == 0) {
          mbar_expect_tx(bars + kBarFullW, kSplitN * kWBytes + kXPhBytes);
          tma4d(base + x_slot(kBlocks), &tmx, prow, 1, l0, b, bars + kBarFullW);
        }
        tma2d(base + kOffW + (t - 2) * kWBytes, &tmw, d0, (2 * t + 1) * kD + prow, bars + kBarFullW);
      }
    }
  } else if (warp == 1) {
    asm volatile("bar.sync 1, 192;" ::: "memory");
    const int grp = b * 8 + dt, seg = lt * 2 + kh;
    const uint32_t gv = reinterpret_cast<const uint32_t*>(gamma + d0)[lane];
    const uint32_t bv = reinterpret_cast<const uint32_t*>(beta + d0)[lane];
    unsigned tag;
    asm volatile("ld.relaxed.gpu.global.u32 %0, [%1];" : "=r"(tag) : "l"(&g_stats[(grp * 8 + seg) * 32 + lane]) : "memory");
    asm volatile("st.shared.u32 [%0], %1;" ::"r"(bars + kOffAux + 4 * lane), "r"(gv) : "memory");
    asm volatile("st.shared.u32 [%0], %1;" ::"r"(bars + kOffAux + 128 + 4 * lane), "r"(bv) : "memory");
    asm volatile("st.shared.u32 [%0], %1;" ::"r"(bars + kOffAux + 256), "r"((tag + 1) & 3) : "memory");
    __syncwarp();
    if (lane == 0) mbar_arrive(bars + kBarAux);
  } else if (warp >= 4) {
    const int tid = threadIdx.x - 128, cw = warp - 4;
    const int g = lane >> 2, q = lane & 3;
    const int grp = b * 8 + dt;
    const int row0 = cw * 16 + g;
    const int seg = lt * 2 + kh;
    const bool tail = (seg == 7);
    asm volatile("bar.sync 1, 192;" ::: "memory");

    uint32_t rbuf, rbar;
    asm volatile("mapa.shared::cluster.u32 %0, %1, %2;" : "=r"(rbuf) : "r"(base + kOffRecv + tid * 8), "r"(kh ^ 1));
    asm volatile("mapa.shared::cluster.u32 %0, %1, %2;" : "=r"(rbar) : "r"(bars + kBarRecv), "r"(kh ^ 1));

    int lrv = cw * 16 + (lane >> 3);
    __nv_bfloat16* op = out + ((size_t)b * kL + seg * 64 + lrv) * kD + d0 + (lane & 7) * 8;
    uint4* recp = &g_stats[(grp * 8) * 32 + cw * 8 + g];
    uint32_t aux_addr = bars + kOffAux + 2 * row0;
    uint32_t st_addr = base + kOffStage + ((lane >> 4) * 8 + (lane & 7)) * 128 + (((2 * cw + ((lane >> 3) & 1)) ^ (lane & 7)) << 4);
    uint32_t ld_addr = base + kOffStage + lrv * 128 + (((lane & 7) ^ (lrv & 7)) << 4);
    uint32_t lbuf = base + kOffRecv + tid * 8;
    int qv = q;
    asm volatile("" : "+r"(dP), "+r"(dO));
    asm volatile("" : "+l"(op), "+l"(recp), "+r"(aux_addr), "+r"(st_addr), "+r"(ld_addr), "+r"(qv));
    asm volatile("" : "+r"(lrv));
    asm volatile("" : "+r"(lbuf));

    float acc[64];
    unsigned tag;
    const uint32_t descW0 = make_desc(base + kOffW), descX0 = make_desc(base + x_slot(0));
    {
      const bool lead = (lane == 0);
      auto step = [&](const uint32_t aD, const uint32_t bD, const uint32_t fb, const uint32_t par, const int scale0) {
        mbar_wait(fb, par);
        wg_fence();
#pragma unroll
        for (int k = 0; k < 4; k++) wgmma_m64n128k16(acc, aD + k * kAK16, bD + k * kBK16, k != 0 ? 1 : scale0);
        wg_commit();
        wg_wait<2>();
        mbar_arrive_if(fb + (kBarEmptyW - kBarFullW), lead);
      };
#pragma unroll 1
      for (int cb = 0; cb < kBlocks - 1; cb++) {
        const uint32_t par = cb & 1, bX = descX0 - par * (kXBlkBytes >> 4);
        uint32_t aD = descW0, bD = bX, fb = bars + kBarFullW;
#pragma unroll 1
        for (int j = 0; j < 8; j++, aD += kAStage, bD += kBRow, fb += 8) step(aD, bD, fb, par, cb | j);
        if (cb == 1) {
          asm volatile("barrier.cluster.wait.acquire.aligned;" ::: "memory");
          mbar_wait(bars + kBarAux, 0);
          asm volatile("ld.shared.u32 %0, [%1];" : "=r"(tag) : "r"(bars + kOffAux + 256) : "memory");
        }
        bD = bX + (kXPhBytes >> 4);
#pragma unroll 1
        for (int j = 0; j < 7; j++, aD += kAStage, bD += kBRow, fb += 8) step(aD, bD, fb, par, 1);
      }
      constexpr uint32_t par = (kBlocks - 1) & 1;
      uint32_t aD = descW0, bD = descX0 - par * (kXBlkBytes >> 4), fb = bars + kBarFullW;
#pragma unroll 1
      for (int j = 0; j < kSplitT; j++, aD += kAStage, bD += kBRow, fb += 8) {
        if (j > 0) mbar_wait(fb + 8 * kSplitN, par);
        step(aD, bD, fb, par, 1);
      }
    }

    float v[32];
    {
      float accO[32];
      const uint32_t aO = descW0 + kSplitT * kAStage;
      wg_fence();
#pragma unroll
      for (int i = 0; i < kHead; i++)
        wgmma_m64n64k16(accO, aO + (i >> 2) * kAStage + (i & 3) * kAK16, dO + (i >> 2) * kBRow + (i & 3) * kBK16, i != 0);
      wg_commit();
      wg_wait<1>();
#define SEND_HALF(SEND)                                                                                                 \
      _Pragma("unroll") for (int j = 0; j < 8; j++)                                                                     \
        asm volatile("st.async.weak.shared::cluster.mbarrier::complete_tx::bytes.v2.b32 [%0], {%1, %2}, [%3];"           \
                     ::"r"(rbuf + j * 1024), "r"(pack_bf16(acc[SEND + 4 * j], acc[SEND + 4 * j + 1])),                  \
                       "r"(pack_bf16(acc[SEND + 4 * j + 2], acc[SEND + 4 * j + 3])), "r"(rbar) : "memory");
      if (kh == 0) { SEND_HALF(32) } else { SEND_HALF(0) }
#undef SEND_HALF
      const int one = (int)(gridDim.x >> 7);
      uint32_t aD = aO + 2 * kAStage, bD = dO + 2 * kBRow;
      auto steps = [&](const int n) {
#pragma unroll 1
        for (int j = 1 - one; j < n; j++, aD += kAStage, bD += kBRow) {
          wg_fence();
#pragma unroll
          for (int k = 0; k < 4; k++) wgmma_m64n64k16(accO, aD + k * kAK16, bD + k * kBK16, 1);
        }
      };
      wg_fence();
#pragma unroll
      for (int i = kHead; i < 8; i++)
        wgmma_m64n64k16(accO, aO + (i >> 2) * kAStage + (i & 3) * kAK16, dO + (i >> 2) * kBRow + (i & 3) * kBK16, 1);
      steps(kSplitN - 2);
      float keep[32];
#pragma unroll
      for (int i = 0; i < 32; i++) keep[i] = kh ? acc[32 + i] : acc[i];
      mbar_wait(bars + kBarFullW, kBlocks & 1);
      mbar_wait(bars + kBarRecv, 0);
      uint32_t r[16];
#pragma unroll
      for (int j = 0; j < 8; j++)
        asm volatile("ld.shared.v2.u32 {%0, %1}, [%2];" : "=r"(r[2 * j]), "=r"(r[2 * j + 1]) : "r"(lbuf + j * 1024) : "memory");
      aD = descW0 - 2 * kAStage; bD = dP;
      steps(kSplitN - 1);
      float u[32];
#pragma unroll
      for (int i = 0; i < 16; i++) {
        u[2 * i] = keep[2 * i] + bf16_lo(r[i]);
        u[2 * i + 1] = keep[2 * i + 1] + bf16_hi(r[i]);
      }
#pragma unroll
      for (int i = 0; i < 32; i++) asm volatile("" : "+f"(u[i]));
      wg_fence();
#pragma unroll
      for (int k = 0; k < 4; k++) wgmma_m64n64k16(accO, aD + k * kAK16, bD + k * kBK16, 1);
      wg_commit();
      wg_wait<0>();
#pragma unroll
      for (int i = 0; i < 32; i++) v[i] = accO[i] + u[i];
    }

    float m0, m1;
    {
      if (tail) {
        static_assert(kTail == 45, "tail masking is written for 45 columns");
        if (qv >= 3) { v[20] = 0.f; v[22] = 0.f; }
        if (qv >= 2) { v[21] = 0.f; v[23] = 0.f; }
#pragma unroll
        for (int i = 24; i < 32; i++) v[i] = 0.f;
      }
      float s0a = v[0], s0b = v[1], s1a = v[2], s1b = v[3];
      float q0a = s0a * s0a, q0b = s0b * s0b, q1a = s1a * s1a, q1b = s1b * s1b;
#pragma unroll
      for (int i = 1; i < 8; i++) {
        const float a0 = v[4 * i], a1 = v[4 * i + 1], a2 = v[4 * i + 2], a3 = v[4 * i + 3];
        s0a += a0; s0b += a1; s1a += a2; s1b += a3;
        q0a = fmaf(a0, a0, q0a); q0b = fmaf(a1, a1, q0b); q1a = fmaf(a2, a2, q1a); q1b = fmaf(a3, a3, q1b);
      }
      float s0 = s0a + s0b, s1 = s1a + s1b, q0 = q0a + q0b, q1 = q1a + q1b;
#pragma unroll
      for (int o = 1; o <= 2; o <<= 1) {
        s0 += __shfl_xor_sync(0xffffffffu, s0, o); s1 += __shfl_xor_sync(0xffffffffu, s1, o);
        q0 += __shfl_xor_sync(0xffffffffu, q0, o); q1 += __shfl_xor_sync(0xffffffffu, q1, o);
      }
      const float inv = tail ? 1.f / kTail : 1.f / 64.f;
      m0 = s0 * inv; m1 = s1 * inv;
      if (qv == 0) {
        uint4 r;
        r.x = (__float_as_uint(m0) & ~3u) | tag; r.y = (__float_as_uint(fmaf(-s0, m0, q0)) & ~3u) | tag;
        r.z = (__float_as_uint(m1) & ~3u) | tag; r.w = (__float_as_uint(fmaf(-s1, m1, q1)) & ~3u) | tag;
        st_rec(recp + seg * 32, r);
      }
    }

    uint16_t gr0, gr1, br0, br1;
    asm volatile("ld.shared.u16 %0, [%1];" : "=h"(gr0) : "r"(aux_addr) : "memory");
    asm volatile("ld.shared.u16 %0, [%1];" : "=h"(gr1) : "r"(aux_addr + 16) : "memory");
    asm volatile("ld.shared.u16 %0, [%1];" : "=h"(br0) : "r"(aux_addr + 128) : "memory");
    asm volatile("ld.shared.u16 %0, [%1];" : "=h"(br1) : "r"(aux_addr + 144) : "memory");

    float a0, a1, b0, b1;
    {
      const uint4* pr = recp + 2 * qv * 32;
      auto stale = [&](const uint4& x, const uint4& y, const unsigned t) {
        uint32_t e0, e1, e2, e3;
        asm("lop3.b32 %0, %1, %2, %3, 0x7e;" : "=r"(e0) : "r"(x.x), "r"(x.y), "r"(t));
        asm("lop3.b32 %0, %1, %2, %3, 0x7e;" : "=r"(e1) : "r"(x.z), "r"(x.w), "r"(t));
        asm("lop3.b32 %0, %1, %2, %3, 0x7e;" : "=r"(e2) : "r"(y.x), "r"(y.y), "r"(t));
        asm("lop3.b32 %0, %1, %2, %3, 0x7e;" : "=r"(e3) : "r"(y.z), "r"(y.w), "r"(t));
        asm("lop3.b32 %0, %1, %2, %3, 0xfe;" : "=r"(e0) : "r"(e0), "r"(e1), "r"(e2));
        return ((e0 | e3) & 3u) != 0;
      };
      spin_until(clock32() + POLL_REL);
      const float cb2 = (qv == 3) ? (float)kTail : 64.f;
      const float g0 = 0.5f * bf16_lo(gr0), g1 = 0.5f * bf16_lo(gr1), h0 = 0.5f * bf16_lo(br0), h1 = 0.5f * bf16_lo(br1);
      int n = 0;
      bool again;
#pragma unroll 1
      do {
        const uint4 ra = ld_rec(pr), rb = ld_rec(pr + 32);
        again = __any_sync(0xffffffffu, stale(ra, rb, tag));
        const float da0 = __uint_as_float(ra.x) - m0, db0 = __uint_as_float(rb.x) - m0;
        const float da1 = __uint_as_float(ra.z) - m1, db1 = __uint_as_float(rb.z) - m1;
        const float ea0 = 64.f * da0, eb0 = cb2 * db0, ea1 = 64.f * da1, eb1 = cb2 * db1;
        float t0 = ea0 + eb0, t1 = ea1 + eb1;
        float u0 = fmaf(ea0, da0, fmaf(eb0, db0, __uint_as_float(ra.y) + __uint_as_float(rb.y)));
        float u1 = fmaf(ea1, da1, fmaf(eb1, db1, __uint_as_float(ra.w) + __uint_as_float(rb.w)));
#pragma unroll
        for (int o = 1; o <= 2; o <<= 1) {
          t0 += __shfl_xor_sync(0xffffffffu, t0, o); t1 += __shfl_xor_sync(0xffffffffu, t1, o);
          u0 += __shfl_xor_sync(0xffffffffu, u0, o); u1 += __shfl_xor_sync(0xffffffffu, u1, o);
        }
        const float dm0 = t0 * (1.f / kL), dm1 = t1 * (1.f / kL);
        const float var0 = fmaxf(fmaf(-t0, dm0, u0), 0.f) * (1.f / kL), var1 = fmaxf(fmaf(-t1, dm1, u1), 0.f) * (1.f / kL);
        float rs0, rs1;
        asm("rsqrt.approx.ftz.f32 %0, %1;" : "=f"(rs0) : "f"(var0 + 1e-5f));
        asm("rsqrt.approx.ftz.f32 %0, %1;" : "=f"(rs1) : "f"(var1 + 1e-5f));
        a0 = rs0 * g0;
        a1 = rs1 * g1;
        b0 = fmaf(-(m0 + dm0), a0, h0);
        b1 = fmaf(-(m1 + dm1), a1, h1);
        if (++n > kSpinLimit) __trap();
      } while (again);
    }

    {
      const int cnt = tail ? kTail : 64;
#pragma unroll
      for (int i = 0; i < 4; i++) {
        uint32_t pk[4];
#pragma unroll
        for (int u = 0; u < 2; u++) {
          const float* w = &v[8 * i + 4 * u];
          pk[2 * u] = pack_bf16(gelu_tanh_half(fmaf(w[0], a0, b0)), gelu_tanh_half(fmaf(w[1], a0, b0)));
          pk[2 * u + 1] = pack_bf16(gelu_tanh_half(fmaf(w[2], a1, b1)), gelu_tanh_half(fmaf(w[3], a1, b1)));
        }
        asm volatile("stmatrix.sync.aligned.m8n8.x4.trans.shared.b16 [%0], {%1, %2, %3, %4};"
                     ::"r"(st_addr + i * 2048), "r"(pk[0]), "r"(pk[1]), "r"(pk[2]), "r"(pk[3]) : "memory");
      }
      asm volatile("bar.sync 2, 128;" ::: "memory");
#pragma unroll
      for (int i = 0; i < 4; i++) {
        const uint4 o = lds128((ld_addr ^ ((i & 1) << 6)) + i * 512);
        if (lrv + 4 * i < cnt)
          asm volatile("st.global.v4.u32 [%0], {%1, %2, %3, %4};" ::"l"(op + (size_t)i * 4 * kD), "r"(o.x), "r"(o.y), "r"(o.z), "r"(o.w) : "memory");
      }
    }
  }
}

typedef CUresult (*EncodeFn)(CUtensorMap*, CUtensorMapDataType, cuuint32_t, void*, const cuuint64_t*, const cuuint64_t*,
                             const cuuint32_t*, const cuuint32_t*, CUtensorMapInterleave, CUtensorMapSwizzle,
                             CUtensorMapL2promotion, CUtensorMapFloatOOBfill);

}

extern "C" void kernel_launch(void* const* d_in, const int* in_sizes, int n_in, void* d_out, int out_size) {
  (void)in_sizes; (void)n_in; (void)out_size;
  static EncodeFn encode = nullptr;
  if (!encode) {
    void* fn = nullptr;
    cudaDriverEntryPointQueryResult qr;
    cudaGetDriverEntryPoint("cuTensorMapEncodeTiled", &fn, cudaEnableDefault, &qr);
    encode = (EncodeFn)fn;
    cudaFuncSetAttribute(conv_stem_kernel, cudaFuncAttributeMaxDynamicSharedMemorySize, kSmemBytes);
  }
  CUtensorMap tmx, tmw;
  {
    cuuint64_t dims[4] = {(cuuint64_t)kD, 2, (cuuint64_t)(kT / 2), (cuuint64_t)kB};
    cuuint64_t strides[3] = {kD * 2, 2 * kD * 2, (cuuint64_t)kT * kD * 2};
    cuuint32_t box[4] = {64, 1, (cuuint32_t)kXRows, 1};
    cuuint32_t es[4] = {1, 1, 1, 1};
    encode(&tmx, CU_TENSOR_MAP_DATA_TYPE_BFLOAT16, 4, d_in[0], dims, strides, box, es, CU_TENSOR_MAP_INTERLEAVE_NONE,
           CU_TENSOR_MAP_SWIZZLE_128B, CU_TENSOR_MAP_L2_PROMOTION_L2_128B, CU_TENSOR_MAP_FLOAT_OOB_FILL_NONE);
  }
  {
    cuuint64_t dims[2] = {(cuuint64_t)kD, (cuuint64_t)kTaps * kD};
    cuuint64_t strides[1] = {kD * 2};
    cuuint32_t box[2] = {64, 64};
    cuuint32_t es[2] = {1, 1};
    encode(&tmw, CU_TENSOR_MAP_DATA_TYPE_BFLOAT16, 2, d_in[1], dims, strides, box, es, CU_TENSOR_MAP_INTERLEAVE_NONE,
           CU_TENSOR_MAP_SWIZZLE_128B, CU_TENSOR_MAP_L2_PROMOTION_L2_128B, CU_TENSOR_MAP_FLOAT_OOB_FILL_NONE);
  }
  conv_stem_kernel<<<128, kThreads, kSmemBytes, cudaStreamPerThread>>>(
      tmx, tmw, (const __nv_bfloat16*)d_in[2], (const __nv_bfloat16*)d_in[3], (__nv_bfloat16*)d_out);
}
```
